```python
import torch

def _softmax(x, axis=-1):
    return torch.softmax(x, dim=axis)
def _gelu(x):
    return torch.nn.functional.gelu(x, approximate="tanh")
def _silu(x):
    return torch.nn.functional.silu(x)
def _sigmoid(x):
    return torch.sigmoid(x)
def _layernorm(x, axis=-1, eps=1e-5):
    m = x.mean(dim=axis, keepdim=True)
    v = x.var(dim=axis, keepdim=True, unbiased=False)
    return (x - m) / torch.sqrt(v + eps)
def _scatter_add(tgt, idx, src, axis=0):
    return tgt.clone().index_add_(axis, idx, src)
def _segment_sum(src, seg, n):
    out = torch.zeros((n,) + src.shape[1:], dtype=src.dtype)
    return out.index_add_(0, seg, src)
def _pad(x, pw):
    flat = tuple(v for pair in reversed(pw) for v in pair)
    return torch.nn.functional.pad(x, flat)

kernel_name = 'concat_heads__mha_block_cached__gqa_block_cached__near_ridge'

def setup_inputs():

    _w = (lambda a: (lambda t: t.to(torch.bfloat16) if t.is_floating_point() else t)(torch.as_tensor(a)))
    def _A_setup():
        B, Sq, D = 8, 224, 1024
        H, Sk, Dh = 32, 1024, 128
        return {
            "x": _w((lambda *s: torch.randn(*s, dtype=torch.bfloat16) * 0.8)(B, Sq, D)),
            "k_cache": _w((lambda *s: torch.randn(*s, dtype=torch.bfloat16) * 0.8)(B, H, Sk, Dh)),
            "v_cache": _w((lambda *s: torch.randn(*s, dtype=torch.bfloat16) * 0.05)(B, H, Sk, Dh)),
            "wq": _w((lambda *s: torch.randn(*s, dtype=torch.bfloat16) * 0.8)(D, H * Dh) * (D ** -0.5)),
            "wo": _w((lambda *s: torch.randn(*s, dtype=torch.bfloat16) * 0.05)(H * Dh, D) * ((H * Dh) ** -0.5)),
        }
    _A_in = _A_setup()

    def _B_setup():
        B, Sq, D = 8, 224, 1024
        Hq, Hkv, Sk, Dh = 32, 32, 1024, 128
        assert Hq % Hkv == 0, (Hq, Hkv)
        return {
            "x": _w((lambda *s: torch.randn(*s, dtype=torch.bfloat16) * 0.8)(B, Sq, D)),
            "k_cache": _w((lambda *s: torch.randn(*s, dtype=torch.bfloat16) * 0.8)(B, Hkv, Sk, Dh)),
            "v_cache": _w((lambda *s: torch.randn(*s, dtype=torch.bfloat16) * 0.05)(B, Hkv, Sk, Dh)),
            "wq": _w((lambda *s: torch.randn(*s, dtype=torch.bfloat16) * 0.8)(D, Hq * Dh) * (D ** -0.5)),
            "wo": _w((lambda *s: torch.randn(*s, dtype=torch.bfloat16) * 0.05)(Hq * Dh, D) * ((Hq * Dh) ** -0.5)),
        }
    _B_in = _B_setup()

    return {
        "A_x": _A_in["x"],
        "A_k_cache": _A_in["k_cache"],
        "A_v_cache": _A_in["v_cache"],
        "A_wq": _A_in["wq"],
        "A_wo": _A_in["wo"],
        "B_x": _B_in["x"],
        "B_k_cache": _B_in["k_cache"],
        "B_v_cache": _B_in["v_cache"],
        "B_wq": _B_in["wq"],
        "B_wo": _B_in["wo"],
    }

def reference(A_x, A_k_cache, A_v_cache, A_wq, A_wo, B_x, B_k_cache, B_v_cache, B_wq, B_wo):
    def _A_ref(x, k_cache, v_cache, wq, wo):
        B, Sq, D = x.shape
        H, Dh = 32, 128
        q = (lambda x, *d: x.permute(*d))((x @ wq).reshape(B, Sq, H, Dh), 0, 2, 1, 3)
        scores = torch.einsum("bhqd,bhkd->bhqk", q, k_cache) * (Dh ** -0.5)
        p = _softmax(scores, axis=-1)
        o = torch.einsum("bhqk,bhkd->bhqd", p, v_cache)
        return (lambda x, *d: x.permute(*d))(o, 0, 2, 1, 3).reshape(B, Sq, H * Dh) @ wo

    def _B_ref(x, k_cache, v_cache, wq, wo):
        B, Sq, D = x.shape
        Hq, Dh = 32, 128
        Hkv = k_cache.shape[1]
        rep = Hq // Hkv
        q = (lambda x, *d: x.permute(*d))((x @ wq).reshape(B, Sq, Hq, Dh), 0, 2, 1, 3)
        k = (lambda x, n, axis: torch.repeat_interleave(x, n, dim=axis))(k_cache, rep, axis=1)
        v = (lambda x, n, axis: torch.repeat_interleave(x, n, dim=axis))(v_cache, rep, axis=1)
        scores = torch.einsum("bhqd,bhkd->bhqk", q, k) * (Dh ** -0.5)
        p = _softmax(scores, axis=-1)
        o = torch.einsum("bhqk,bhkd->bhqd", p, v)
        return (lambda x, *d: x.permute(*d))(o, 0, 2, 1, 3).reshape(B, Sq, Hq * Dh) @ wo

    a = _A_ref(A_x, A_k_cache, A_v_cache, A_wq, A_wo)
    b = _B_ref(B_x, B_k_cache, B_v_cache, B_wq, B_wo)
    return torch.concatenate([a, b], axis=-1)
```

```cpp
#include <cuda_runtime.h>
#include <cuda_bf16.h>
#include <cuda.h>
#include <stdint.h>

namespace {

constexpr int kB = 8, kSq = 224, kD = 1024, kH = 32, kSk = 1024, kDh = 128;
constexpr int kRows = kB * kSq;
constexpr int kHD = kH * kDh;

constexpr int PROJ_BYTES = 22528;
constexpr int KV_BYTES = 16384;
constexpr int OFF_RING = 0;
constexpr int RING_BYTES = 137 * 1024;
constexpr int OFF_P = RING_BYTES;
constexpr int P_WG = 14336;
constexpr int OFF_Q = OFF_P + 2 * P_WG;
constexpr int Q_HALF = 28672;
constexpr int OFF_RED = OFF_Q + 2 * Q_HALF;
constexpr int OFF_RES = OFF_RED + 3584;
constexpr int OFF_BAR = OFF_RES + 1792;
constexpr int NBAR = 16;
constexpr int BAR_FULL = OFF_BAR, BAR_EMPTY = OFF_BAR + 128, BAR_ORDY = OFF_BAR + 256, BAR_EXT = OFF_BAR + 272,
              OFF_FLAG = OFF_BAR + 280;
constexpr int SMEM_BYTES = OFF_BAR + 288;
static_assert(SMEM_BYTES <= 232448, "shared memory budget");

struct Params {
  CUtensorMap x[2], wq[2], k[2], v[2], wo[2], o_st, o_ld, out_st;
  const char *k_ptr[2], *v_ptr[2];
  char* o_ptr;
  uint32_t zero;
};

__device__ __nv_bfloat16 g_o[2 * kRows * kHD];
__device__ unsigned int g_cnt[16 * 4 * 32];
__device__ unsigned int g_epoch[132];

__device__ __forceinline__ uint32_t smem_u32(const void* p) { return (uint32_t)__cvta_generic_to_shared(p); }
__device__ __forceinline__ void mbar_init(uint32_t bar, uint32_t cnt) {
  asm volatile("mbarrier.init.shared::cta.b64 [%0], %1;" ::"r"(bar), "r"(cnt) : "memory");
}
__device__ __forceinline__ void mbar_expect_tx(uint32_t bar, uint32_t bytes) {
  asm volatile("mbarrier.arrive.expect_tx.shared::cta.b64 _, [%0], %1;" ::"r"(bar), "r"(bytes) : "memory");
}
__device__ __forceinline__ void mbar_arrive(uint32_t bar) {
  asm volatile("mbarrier.arrive.shared::cta.b64 _, [%0];" ::"r"(bar) : "memory");
}
__device__ __forceinline__ uint32_t map_to_cta(uint32_t addr, uint32_t cta) {
  uint32_t r;
  asm("mapa.shared::cluster.u32 %0, %1, %2;" : "=r"(r) : "r"(addr), "r"(cta));
  return r;
}
__device__ __forceinline__ void mbar_wait(uint32_t bar, uint32_t parity) {
  asm volatile(
      "{\n.reg .pred p;\n.reg .u32 n;\n"
      "mbarrier.try_wait.parity.shared::cta.b64 p, [%0], %1;\n"
      "@p bra DONE;\n"
      "mov.u32 n, 0;\n"
      "LOOP:\n"
      "mbarrier.try_wait.parity.shared::cta.b64 p, [%0], %1;\n"
      "@p bra DONE;\n"
      "add.u32 n, n, 1;\n"
      "setp.lt.u32 p, n, 1048576;\n"
      "@p bra LOOP;\n"
      "trap;\n"
      "DONE:\n}"
      ::"r"(bar), "r"(parity)
      : "memory");
}
__device__ __forceinline__ void mbar_wait_sleep(uint32_t bar, uint32_t parity) {
  asm volatile(
      "{\n.reg .pred p;\n.reg .u32 n;\n"
      "mov.u32 n, 0;\n"
      "LOOP:\n"
      "mbarrier.try_wait.parity.shared::cta.b64 p, [%0], %1, 300;\n"
      "@p bra DONE;\n"
      "add.u32 n, n, 1;\n"
      "setp.lt.u32 p, n, 1048576;\n"
      "@p bra LOOP;\n"
      "trap;\n"
      "DONE:\n}"
      ::"r"(bar), "r"(parity)
      : "memory");
}
__device__ __forceinline__ void flag_wait(const unsigned* ptr, unsigned target) {
  asm volatile(
      "{\n.reg .pred p;\n.reg .u32 n, v;\n"
      "mov.u32 n, 0;\n"
      "LOOP:\n"
      "ld.acquire.gpu.global.u32 v, [%0];\n"
      "sub.u32 v, v, %1;\n"
      "setp.ge.s32 p, v, 0;\n"
      "@p bra DONE;\n"
      "add.u32 n, n, 1;\n"
      "setp.lt.u32 p, n, 4194304;\n"
      "@p bra LOOP;\n"
      "trap;\n"
      "DONE:\n}"
      ::"l"(ptr), "r"(target)
      : "memory");
}
__device__ __forceinline__ void flag_wait_soft(const unsigned* ptr, unsigned target) {
  asm volatile(
      "{\n.reg .pred p;\n.reg .u32 n, v;\n"
      "mov.u32 n, 0;\n"
      "LOOP:\n"
      "ld.relaxed.gpu.global.u32 v, [%0];\n"
      "sub.u32 v, v, %1;\n"
      "setp.ge.s32 p, v, 0;\n"
      "@p bra DONE;\n"
      "nanosleep.u32 100;\n"
      "add.u32 n, n, 1;\n"
      "setp.lt.u32 p, n, 20000;\n"
      "@p bra LOOP;\n"
      "DONE:\n}"
      ::"l"(ptr), "r"(target)
      : "memory");
}
__device__ __forceinline__ bool elect_one() {
  uint32_t pred;
  asm volatile("{\n.reg .pred p;\nelect.sync _|p, 0xffffffff;\nselp.u32 %0, 1, 0, p;\n}" : "=r"(pred));
  return pred != 0;
}
__device__ __forceinline__ void tma_load_3d(uint32_t dst, const CUtensorMap* tm, int c0, int c1, int c2, uint32_t bar) {
  asm volatile("cp.async.bulk.tensor.3d.shared::cluster.global.mbarrier::complete_tx::bytes [%0], [%1, {%3, %4, %5}], [%2];" ::"r"(dst),
               "l"(tm), "r"(bar), "r"(c0), "r"(c1), "r"(c2)
               : "memory");
}
__device__ __forceinline__ void tma_load_3d_hint(uint32_t dst, const CUtensorMap* tm, int c0, int c1, int c2, uint32_t bar, uint64_t pol) {
  asm volatile(
      "cp.async.bulk.tensor.3d.shared::cluster.global.mbarrier::complete_tx::bytes.L2::cache_hint [%0], [%1, {%3, %4, %5}], [%2], %6;" ::"r"(dst),
      "l"(tm), "r"(bar), "r"(c0), "r"(c1), "r"(c2), "l"(pol)
      : "memory");
}
__device__ __forceinline__ void tma_load_2d_mc(uint32_t dst, const CUtensorMap* tm, int c0, int c1, uint32_t bar, uint16_t mask) {
  asm volatile(
      "cp.async.bulk.tensor.2d.shared::cluster.global.mbarrier::complete_tx::bytes.multicast::cluster [%0], [%1, {%3, %4}], [%2], %5;" ::"r"(dst),
      "l"(tm), "r"(bar), "r"(c0), "r"(c1), "h"(mask)
      : "memory");
}
__device__ __forceinline__ void tma_store_2d(const CUtensorMap* tm, uint32_t src, int c0, int c1) {
  asm volatile("cp.async.bulk.tensor.2d.global.shared::cta.bulk_group [%0, {%2, %3}], [%1];" ::"l"(tm), "r"(src), "r"(c0), "r"(c1) : "memory");
}
__device__ __forceinline__ void bulk_prefetch(const void* a, uint32_t bytes, uint64_t pol) {
  asm volatile("cp.async.bulk.prefetch.L2.global.L2::cache_hint [%0], %1, %2;" ::"l"(a), "r"(bytes), "l"(pol) : "memory");
}
__device__ __forceinline__ uint64_t policy_evict_first() {
  uint64_t pol;
  asm volatile("createpolicy.fractional.L2::evict_first.b64 %0, 1.0;" : "=l"(pol));
  return pol;
}
__device__ __forceinline__ void wg_fence() { asm volatile("wgmma.fence.sync.aligned;" ::: "memory"); }
__device__ __forceinline__ void wg_commit() { asm volatile("wgmma.commit_group.sync.aligned;" ::: "memory"); }
template <int N>
__device__ __forceinline__ void wg_wait() {
  asm volatile("wgmma.wait_group.sync.aligned %0;" ::"n"(N) : "memory");
}
template <int N>
__device__ __forceinline__ void pin(float (&d)[N]) {
#pragma unroll
  for (int i = 0; i < N; i++) asm volatile("" : "+f"(d[i])::"memory");
}
constexpr uint32_t DESC_SW128 = 0x40000040u;
constexpr uint32_t DESC_SW64 = 0x80000020u;
__device__ __forceinline__ uint32_t desc_lo(uint32_t addr) { return ((addr & 0x3FFFF) >> 4) | (1u << 16); }
__device__ __forceinline__ uint64_t desc(uint32_t lo, uint32_t hi) { return ((uint64_t)hi << 32) | lo; }
__device__ __forceinline__ uint32_t pack_bf16(float lo, float hi) {
  uint32_t r;
  asm("cvt.rn.bf16x2.f32 %0, %1, %2;" : "=r"(r) : "f"(hi), "f"(lo));
  return r;
}
__device__ __forceinline__ float ex2(float x) {
  float y;
  asm("ex2.approx.ftz.f32 %0, %1;" : "=f"(y) : "f"(x));
  return y;
}
__device__ __forceinline__ float rcp_fast(float x) {
  float y;
  asm("rcp.approx.ftz.f32 %0, %1;" : "=f"(y) : "f"(x));
  return y;
}
__device__ __forceinline__ void stsm_x4_t(uint32_t addr, uint32_t r0, uint32_t r1, uint32_t r2, uint32_t r3) {
  asm volatile("stmatrix.sync.aligned.m8n8.x4.trans.shared.b16 [%0], {%1,%2,%3,%4};" ::"r"(addr), "r"(r0), "r"(r1), "r"(r2), "r"(r3)
               : "memory");
}
__device__ __forceinline__ void fence_async_smem() { asm volatile("fence.proxy.async.shared::cta;" ::: "memory"); }
__device__ __forceinline__ void bar_sync(int id, int n) { asm volatile("bar.sync %0, %1;" ::"r"(id), "r"(n) : "memory"); }
__device__ __forceinline__ void bar_arrive(int id, int n) { asm volatile("bar.arrive %0, %1;" ::"r"(id), "r"(n) : "memory"); }
__device__ __forceinline__ bool bar_or(int id, int n, bool pred) {
  uint32_t r;
  asm volatile("{\n.reg .pred p, q;\nsetp.ne.b32 p, %3, 0;\nbar.red.or.pred q, %1, %2, p;\nselp.u32 %0, 1, 0, q;\n}"
               : "=r"(r)
               : "r"(id), "r"(n), "r"((uint32_t)pred)
               : "memory");
  return r != 0;
}
__device__ __forceinline__ void st_shared_u32(uint32_t addr, uint32_t v) {
  asm volatile("st.shared.u32 [%0], %1;" ::"r"(addr), "r"(v) : "memory");
}
__device__ __forceinline__ uint32_t ld_shared_u32(uint32_t addr) {
  uint32_t v;
  asm volatile("ld.shared.u32 %0, [%1];" : "=r"(v) : "r"(addr) : "memory");
  return v;
}
__device__ __forceinline__ void st_shared_u4(uint32_t addr, uint32_t a, uint32_t b, uint32_t c, uint32_t d) {
  asm volatile("st.shared.v4.u32 [%0], {%1, %2, %3, %4};" ::"r"(addr), "r"(a), "r"(b), "r"(c), "r"(d) : "memory");
}
__device__ __forceinline__ uint4 ld_shared_u4(uint32_t addr) {
  uint4 v;
  asm volatile("ld.shared.v4.u32 {%0, %1, %2, %3}, [%4];" : "=r"(v.x), "=r"(v.y), "=r"(v.z), "=r"(v.w) : "r"(addr) : "memory");
  return v;
}
__device__ __forceinline__ void st_global_u4(void* ptr, uint4 v) {
  asm volatile("st.global.v4.u32 [%0], {%1, %2, %3, %4};" ::"l"(ptr), "r"(v.x), "r"(v.y), "r"(v.z), "r"(v.w) : "memory");
}
__device__ __forceinline__ void st_shared_f2(uint32_t addr, float a, float b) {
  asm volatile("st.shared.v2.f32 [%0], {%1, %2};" ::"r"(addr), "f"(a), "f"(b) : "memory");
}
__device__ __forceinline__ float2 ld_shared_f2(uint32_t addr) {
  float2 v;
  asm volatile("ld.shared.v2.f32 {%0, %1}, [%2];" : "=f"(v.x), "=f"(v.y) : "r"(addr) : "memory");
  return v;
}

template <int TA>
__device__ __forceinline__ void wgmma_n112(float (&d)[56], uint64_t da, uint64_t db, int scaleD) {
  asm volatile(
      "{\n.reg .pred p;\nsetp.ne.b32 p, %58, 0;\n"
      "wgmma.mma_async.sync.aligned.m64n112k16.f32.bf16.bf16 "
      "{%0, %1, %2, %3, %4, %5, %6, %7, %8, %9, %10, %11, %12, %13, %14, %15, %16, %17, %18, %19, %20, %21, %22, %23, %24, %25, %26, %27, %28, %29, %30, %31, %32, %33, %34, %35, %36, %37, %38, %39, %40, %41, %42, %43, %44, %45, %46, %47, %48, %49, %50, %51, %52, %53, %54, %55}, "
      "%56, %57, p, 1, 1, %59, 0;\n}\n"
      : "+f"(d[0]), "+f"(d[1]), "+f"(d[2]), "+f"(d[3]), "+f"(d[4]), "+f"(d[5]), "+f"(d[6]), "+f"(d[7]), "+f"(d[8]), "+f"(d[9]), "+f"(d[10]), "+f"(d[11]), "+f"(d[12]), "+f"(d[13]), "+f"(d[14]), "+f"(d[15]), "+f"(d[16]), "+f"(d[17]), "+f"(d[18]), "+f"(d[19]), "+f"(d[20]), "+f"(d[21]), "+f"(d[22]), "+f"(d[23]), "+f"(d[24]), "+f"(d[25]), "+f"(d[26]), "+f"(d[27]), "+f"(d[28]), "+f"(d[29]), "+f"(d[30]), "+f"(d[31]), "+f"(d[32]), "+f"(d[33]), "+f"(d[34]), "+f"(d[35]), "+f"(d[36]), "+f"(d[37]), "+f"(d[38]), "+f"(d[39]), "+f"(d[40]), "+f"(d[41]), "+f"(d[42]), "+f"(d[43]), "+f"(d[44]), "+f"(d[45]), "+f"(d[46]), "+f"(d[47]), "+f"(d[48]), "+f"(d[49]), "+f"(d[50]), "+f"(d[51]), "+f"(d[52]), "+f"(d[53]), "+f"(d[54]), "+f"(d[55])
      : "l"(da), "l"(db), "r"(scaleD), "n"(TA));
}
template <int TA>
__device__ __forceinline__ void wgmma_n112_first(float (&d)[56], uint64_t da, uint64_t db) {
  asm volatile(
      "wgmma.mma_async.sync.aligned.m64n112k16.f32.bf16.bf16 "
      "{%0, %1, %2, %3, %4, %5, %6, %7, %8, %9, %10, %11, %12, %13, %14, %15, %16, %17, %18, %19, %20, %21, %22, %23, %24, %25, %26, %27, %28, %29, %30, %31, %32, %33, %34, %35, %36, %37, %38, %39, %40, %41, %42, %43, %44, %45, %46, %47, %48, %49, %50, %51, %52, %53, %54, %55}, "
      "%56, %57, 0, 1, 1, %58, 0;\n"
      : "=f"(d[0]), "=f"(d[1]), "=f"(d[2]), "=f"(d[3]), "=f"(d[4]), "=f"(d[5]), "=f"(d[6]), "=f"(d[7]), "=f"(d[8]), "=f"(d[9]), "=f"(d[10]), "=f"(d[11]), "=f"(d[12]), "=f"(d[13]), "=f"(d[14]), "=f"(d[15]), "=f"(d[16]), "=f"(d[17]), "=f"(d[18]), "=f"(d[19]), "=f"(d[20]), "=f"(d[21]), "=f"(d[22]), "=f"(d[23]), "=f"(d[24]), "=f"(d[25]), "=f"(d[26]), "=f"(d[27]), "=f"(d[28]), "=f"(d[29]), "=f"(d[30]), "=f"(d[31]), "=f"(d[32]), "=f"(d[33]), "=f"(d[34]), "=f"(d[35]), "=f"(d[36]), "=f"(d[37]), "=f"(d[38]), "=f"(d[39]), "=f"(d[40]), "=f"(d[41]), "=f"(d[42]), "=f"(d[43]), "=f"(d[44]), "=f"(d[45]), "=f"(d[46]), "=f"(d[47]), "=f"(d[48]), "=f"(d[49]), "=f"(d[50]), "=f"(d[51]), "=f"(d[52]), "=f"(d[53]), "=f"(d[54]), "=f"(d[55])
      : "l"(da), "l"(db), "n"(TA));
}

template <int TA>
__device__ __forceinline__ void wgmma_n224(float (&d)[112], uint64_t da, uint64_t db, int scaleD) {
  asm volatile(
      "{\n.reg .pred p;\nsetp.ne.b32 p, %114, 0;\n"
      "wgmma.mma_async.sync.aligned.m64n224k16.f32.bf16.bf16 "
      "{%0, %1, %2, %3, %4, %5, %6, %7, %8, %9, %10, %11, %12, %13, %14, %15, %16, %17, %18, %19, %20, %21, %22, %23, %24, %25, %26, %27, %28, %29, %30, %31, %32, %33, %34, %35, %36, %37, %38, %39, %40, %41, %42, %43, %44, %45, %46, %47, %48, %49, %50, %51, %52, %53, %54, %55, %56, %57, %58, %59, %60, %61, %62, %63, %64, %65, %66, %67, %68, %69, %70, %71, %72, %73, %74, %75, %76, %77, %78, %79, %80, %81, %82, %83, %84, %85, %86, %87, %88, %89, %90, %91, %92, %93, %94, %95, %96, %97, %98, %99, %100, %101, %102, %103, %104, %105, %106, %107, %108, %109, %110, %111}, "
      "%112, %113, p, 1, 1, %115, 0;\n}\n"
      : "+f"(d[0]), "+f"(d[1]), "+f"(d[2]), "+f"(d[3]), "+f"(d[4]), "+f"(d[5]), "+f"(d[6]), "+f"(d[7]), "+f"(d[8]), "+f"(d[9]), "+f"(d[10]), "+f"(d[11]), "+f"(d[12]), "+f"(d[13]), "+f"(d[14]), "+f"(d[15]), "+f"(d[16]), "+f"(d[17]), "+f"(d[18]), "+f"(d[19]), "+f"(d[20]), "+f"(d[21]), "+f"(d[22]), "+f"(d[23]), "+f"(d[24]), "+f"(d[25]), "+f"(d[26]), "+f"(d[27]), "+f"(d[28]), "+f"(d[29]), "+f"(d[30]), "+f"(d[31]), "+f"(d[32]), "+f"(d[33]), "+f"(d[34]), "+f"(d[35]), "+f"(d[36]), "+f"(d[37]), "+f"(d[38]), "+f"(d[39]), "+f"(d[40]), "+f"(d[41]), "+f"(d[42]), "+f"(d[43]), "+f"(d[44]), "+f"(d[45]), "+f"(d[46]), "+f"(d[47]), "+f"(d[48]), "+f"(d[49]), "+f"(d[50]), "+f"(d[51]), "+f"(d[52]), "+f"(d[53]), "+f"(d[54]), "+f"(d[55]), "+f"(d[56]), "+f"(d[57]), "+f"(d[58]), "+f"(d[59]), "+f"(d[60]), "+f"(d[61]), "+f"(d[62]), "+f"(d[63]), "+f"(d[64]), "+f"(d[65]), "+f"(d[66]), "+f"(d[67]), "+f"(d[68]), "+f"(d[69]), "+f"(d[70]), "+f"(d[71]), "+f"(d[72]), "+f"(d[73]), "+f"(d[74]), "+f"(d[75]), "+f"(d[76]), "+f"(d[77]), "+f"(d[78]), "+f"(d[79]), "+f"(d[80]), "+f"(d[81]), "+f"(d[82]), "+f"(d[83]), "+f"(d[84]), "+f"(d[85]), "+f"(d[86]), "+f"(d[87]), "+f"(d[88]), "+f"(d[89]), "+f"(d[90]), "+f"(d[91]), "+f"(d[92]), "+f"(d[93]), "+f"(d[94]), "+f"(d[95]), "+f"(d[96]), "+f"(d[97]), "+f"(d[98]), "+f"(d[99]), "+f"(d[100]), "+f"(d[101]), "+f"(d[102]), "+f"(d[103]), "+f"(d[104]), "+f"(d[105]), "+f"(d[106]), "+f"(d[107]), "+f"(d[108]), "+f"(d[109]), "+f"(d[110]), "+f"(d[111])
      : "l"(da), "l"(db), "r"(scaleD), "n"(TA));
}


#define SCHED_FENCE() \
  asm volatile("{\n.reg .pred p;\nsetp.eq.u32 p, %0, 0x7fffffff;\nAGAIN:\n@p nanosleep.u32 0;\n@p bra.uni AGAIN;\n}" ::"r"(sb) : "memory")

constexpr uint32_t PROJ16 = PROJ_BYTES / 16, KV16 = KV_BYTES / 16, KV_BASE16 = 512;
constexpr uint32_t kDepKV = 0x77655433, kDepProj = 0x07764320;
static_assert(KV_BASE16 * 16 + 8 * KV_BYTES <= RING_BYTES && 6 * PROJ_BYTES <= RING_BYTES && 7 * PROJ_BYTES <= OFF_Q &&
              10 * PROJ_BYTES <= OFF_RED, "ring geometry");
__device__ __forceinline__ uint32_t kv_off16(uint32_t i) { return KV_BASE16 + (i & 7) * KV16; }
__device__ __forceinline__ uint32_t proj_next16(uint32_t prev, int it, bool out_proj) {
  const uint32_t o = prev + PROJ16;
  return o == (out_proj ? 10 * PROJ16 : (it <= 14 ? 7 * PROJ16 : 6 * PROJ16)) ? 0u : o;
}
__device__ __forceinline__ bool kv_is_k(int i) { return (i == 0) || ((i & 1) && i != 31); }
__device__ __forceinline__ int kv_tile(int i) { return kv_is_k(i) ? ((i + 1) >> 1) : ((i - 1) >> 1); }

struct Ctx {
  uint32_t sb;
  uint32_t ring16;
  uint32_t rel;
  uint32_t do_rel;
};
__device__ __forceinline__ uint32_t full_bar(const Ctx& c, uint32_t n) { return c.sb + BAR_FULL + (n & (NBAR - 1)) * 8; }
__device__ __forceinline__ uint32_t stage_parity(uint32_t n) { return (n >> 4) & 1; }
__device__ __forceinline__ void release_stage(const Ctx& c, uint32_t n) {
  asm volatile(
      "{\n.reg .pred p, q;\nelect.sync _|p, 0xffffffff;\nsetp.ne.and.u32 q, %1, 0, p;\n"
      "@q mbarrier.arrive.shared::cluster.b64 _, [%0];\n}" ::"r"(c.rel + (n & (NBAR - 1)) * 8), "r"(c.do_rel)
      : "memory");
}

__device__ __forceinline__ void store_tile_t(uint32_t addr, const float (&a)[56]) {
#pragma unroll
  for (int c = 0; c < 14; c += 2) {
    stsm_x4_t(addr + c * 1024, pack_bf16(a[4 * c + 0], a[4 * c + 1]), pack_bf16(a[4 * c + 2], a[4 * c + 3]),
              pack_bf16(a[4 * c + 4], a[4 * c + 5]), pack_bf16(a[4 * c + 6], a[4 * c + 7]));
  }
}

__device__ __forceinline__ void issue_s(uint32_t k16, uint32_t q16, float (&s)[56]) {
  uint64_t da = desc(k16, DESC_SW128), db = desc(q16, DESC_SW128);
  asm volatile("" : "+l"(da), "+l"(db));
  wgmma_n112_first<0>(s, da, db);
#pragma unroll
  for (int kk = 1; kk < 8; kk++)
    wgmma_n112<0>(s, da + ((kk >> 2) * 512 + (kk & 3) * 2), db + ((kk >> 2) * (Q_HALF >> 4) + (kk & 3) * 2), 1);
}
__device__ __forceinline__ void issue_pv(uint32_t v16, uint32_t p16, float (&o0)[56], float (&o1)[56], int acc) {
  uint64_t da = desc(v16, DESC_SW128), db = desc(p16, DESC_SW128);
  asm volatile("" : "+l"(da), "+l"(db));
#pragma unroll
  for (int kk = 0; kk < 4; kk++) {
    wgmma_n112<1>(o0, da + kk * 128, db + kk * 2, kk == 0 ? acc : 1);
    wgmma_n112<1>(o1, da + (512 + kk * 128), db + kk * 2, kk == 0 ? acc : 1);
  }
}

constexpr float kScale = 0.08838834764831845f * 1.4426950408889634f;
constexpr float kSumLimit = 16777216.0f;

__device__ __forceinline__ bool exact_tile(uint32_t red_addr, uint32_t res_addr, int bar_wg, int bar_vote, int lane, int wq4, bool fresh,
                                           bool summed, const float (&s)[56], uint32_t (&pk)[28], float (&nm)[14], float (&l)[28],
                                           float (&o0)[56], float (&o1)[56]) {
#pragma unroll
  for (int c = 0; c < 14; c++) {
    float v0 = fmaxf(s[4 * c], s[4 * c + 2]), v1 = fmaxf(s[4 * c + 1], s[4 * c + 3]);
#pragma unroll
    for (int m = 4; m <= 16; m <<= 1) {
      v0 = fmaxf(v0, __shfl_xor_sync(0xffffffff, v0, m));
      v1 = fmaxf(v1, __shfl_xor_sync(0xffffffff, v1, m));
    }
    if (lane < 4) st_shared_f2(red_addr + wq4 * 448 + c * 32 + lane * 8, v0, v1);
  }
  bar_sync(bar_wg, 128);
  bool big = false;
#pragma unroll
  for (int c = 0; c < 14; c++) {
    const uint32_t a = red_addr + c * 32 + (lane & 3) * 8;
    const float2 x0 = ld_shared_f2(a), x1 = ld_shared_f2(a + 448), x2 = ld_shared_f2(a + 896), x3 = ld_shared_f2(a + 1344);
    float m0 = fmaxf(fmaxf(x0.x, x1.x), fmaxf(x2.x, x3.x)), m1 = fmaxf(fmaxf(x0.y, x1.y), fmaxf(x2.y, x3.y));
    float2 res = make_float2(0.f, 0.f);
    const float2 tm = ld_shared_f2(res_addr + c * 32 + (lane & 3) * 8);
    if (!fresh) {
      m0 = fmaxf(m0, tm.x);
      m1 = fmaxf(m1, tm.y);
      if (!(fabsf(tm.x - tm.y) <= 40.f)) res = tm;
    }
    const float d = fmaxf(m0, m1);
    const bool far = !(fabsf((m0 - d) - (m1 - d)) <= 40.f);
    const float d0 = far ? m0 : d, d1 = far ? m1 : d;
    big = big || far;
    nm[c] -= d;
    const float p0 = ex2(s[4 * c] - d0), p1 = ex2(s[4 * c + 1] - d1), p2 = ex2(s[4 * c + 2] - d0), p3 = ex2(s[4 * c + 3] - d1);
    const float h0 = ex2(0.5f * (res.x - d0)), h1 = ex2(0.5f * (res.y - d1));
    const float a0 = h0 * h0, a1 = h1 * h1;
    const bool k0 = !fresh && l[2 * c] < 3.0e38f, k1 = !fresh && l[2 * c + 1] < 3.0e38f;
    l[2 * c] = (k0 ? l[2 * c] * h0 * h0 : 0.f) + ((summed && k0) ? 0.f : p0 + p2);
    l[2 * c + 1] = (k1 ? l[2 * c + 1] * h1 * h1 : 0.f) + ((summed && k1) ? 0.f : p1 + p3);
    o0[4 * c] *= a0; o0[4 * c + 2] *= a0; o0[4 * c + 1] *= a1; o0[4 * c + 3] *= a1;
    o1[4 * c] *= a0; o1[4 * c + 2] *= a0; o1[4 * c + 1] *= a1; o1[4 * c + 3] *= a1;
    pk[2 * c] = pack_bf16(p0, p1);
    pk[2 * c + 1] = pack_bf16(p2, p3);
    if (wq4 == 0 && lane < 4) st_shared_f2(res_addr + 896 + c * 32 + lane * 8, m0 - d, m1 - d);
  }
  big = __any_sync(0xffffffff, bar_or(bar_vote, 128, big));
  if (wq4 == 0 && lane < 4) {
#pragma unroll
    for (int c = 0; c < 14; c++) {
      const float2 v = ld_shared_f2(res_addr + 896 + c * 32 + lane * 8);
      st_shared_f2(res_addr + c * 32 + lane * 8, v.x, v.y);
    }
  }
  return big;
}

template <int C0, int C1>
__device__ __forceinline__ void exp_cols(float (&s)[56], const float (&nm)[14]) {
#pragma unroll
  for (int i = 4 * C0; i < 4 * C1; i++) s[i] = ex2(fmaf(s[i], kScale, nm[i >> 2]));
}
template <int C0, int C1>
__device__ __forceinline__ void sum_pack_cols(const float (&s)[56], uint32_t (&pk)[28], float (&l)[28], float& t0, float& t1) {
#pragma unroll
  for (int c = C0; c < C1; c++) {
    const float u0 = s[4 * c] + s[4 * c + 2], u1 = s[4 * c + 1] + s[4 * c + 3];
    l[2 * c] += u0;
    l[2 * c + 1] += u1;
    t0 = c == 0 ? u0 : t0 + u0;
    t1 = c == 0 ? u1 : t1 + u1;
    pk[2 * c] = pack_bf16(s[4 * c], s[4 * c + 1]);
    pk[2 * c + 1] = pack_bf16(s[4 * c + 2], s[4 * c + 3]);
  }
}
template <int I0, int I1>
__device__ __forceinline__ void pin_range(float (&s)[56]) {
#pragma unroll
  for (int i = I0; i < I1; i++) asm volatile("" : "+f"(s[i])::"memory");
}
template <int C0, int C1>
__device__ __forceinline__ void pin_p(uint32_t (&pk)[28], float (&l)[28]) {
#pragma unroll
  for (int c = C0; c < C1; c++) asm volatile("" : "+r"(pk[2 * c]), "+r"(pk[2 * c + 1]), "+f"(l[2 * c]), "+f"(l[2 * c + 1])::"memory");
}
template <int C0, int C1>
__device__ __forceinline__ void store_p(uint32_t addr, const uint32_t (&pk)[28]) {
#pragma unroll
  for (int c = C0; c < C1; c += 2) stsm_x4_t(addr + c * 1024, pk[2 * c], pk[2 * c + 1], pk[2 * c + 2], pk[2 * c + 3]);
}

__device__ __forceinline__ float first_reference(uint32_t red_addr, int bar_wg, int wq4, const float (&s)[56]) {
  float m[4];
#pragma unroll
  for (int i = 0; i < 4; i++) {
    m[i] = s[14 * i];
#pragma unroll
    for (int k = 1; k < 14; k++) m[i] = fmaxf(m[i], s[14 * i + k]);
  }
  int b = __float_as_int(fmaxf(fmaxf(m[0], m[1]), fmaxf(m[2], m[3])));
  b ^= (b >> 31) & 0x7fffffff;
  b = __reduce_max_sync(0xffffffff, b);
  st_shared_u32(red_addr + wq4 * 4, (uint32_t)b);
  bar_sync(bar_wg, 128);
  const uint4 v = ld_shared_u4(red_addr);
  b = max(max((int)v.x, (int)v.y), max((int)v.z, (int)v.w));
  b ^= (b >> 31) & 0x7fffffff;
  return __int_as_float(b) * -kScale;
}

__device__ __forceinline__ float xchg_add(bool hi, float lo_val, float hi_val, int mask) {
  return (hi ? hi_val : lo_val) + __shfl_xor_sync(0xffffffff, hi ? lo_val : hi_val, mask);
}
__device__ __forceinline__ void reduce_l_lanes(int lane, const float (&l)[28], float (&c)[4]) {
  const bool b4 = lane & 16, b3 = lane & 8, b2 = lane & 4;
  float a[14], b[8];
#pragma unroll
  for (int k = 0; k < 14; k++) a[k] = xchg_add(b4, l[k], l[14 + k], 16);
#pragma unroll
  for (int k = 0; k < 7; k++) b[k] = xchg_add(b3, a[k], a[7 + k], 8);
  b[7] = 0.f;
#pragma unroll
  for (int k = 0; k < 4; k++) c[k] = xchg_add(b2, b[k], b[4 + k], 4);
}
__device__ __forceinline__ void reduce_l_warps(uint32_t red_addr, int bar_wg, int lane, int wq4, const float (&c)[4], float (&l)[28]) {
  const uint32_t dst = red_addr + wq4 * 448 + (lane & 3) * 112 + (((lane & 16) ? 14 : 0) + ((lane & 8) ? 7 : 0) + (lane & 4)) * 4;
  st_shared_u32(dst, __float_as_uint(c[0]));
  st_shared_u32(dst + 4, __float_as_uint(c[1]));
  st_shared_u32(dst + 8, __float_as_uint(c[2]));
  if (!(lane & 4)) st_shared_u32(dst + 12, __float_as_uint(c[3]));
  bar_sync(bar_wg, 128);
  const int x = wq4 * 32 + lane;
  if (x < 112) {
    const uint32_t p = red_addr + x * 4;
    const float v = (__uint_as_float(ld_shared_u32(p)) + __uint_as_float(ld_shared_u32(p + 448))) +
                    (__uint_as_float(ld_shared_u32(p + 896)) + __uint_as_float(ld_shared_u32(p + 1344)));
    st_shared_u32(p, __float_as_uint(rcp_fast(v)));
  }
  bar_sync(bar_wg, 128);
#pragma unroll
  for (int k = 0; k < 7; k++) {
    const uint4 v = ld_shared_u4(red_addr + (lane & 3) * 112 + k * 16);
    l[4 * k] = __uint_as_float(v.x);
    l[4 * k + 1] = __uint_as_float(v.y);
    l[4 * k + 2] = __uint_as_float(v.z);
    l[4 * k + 3] = __uint_as_float(v.w);
  }
}

__global__ void __cluster_dims__(2, 1, 1) __launch_bounds__(384, 1) fused_kernel(const __grid_constant__ Params p) {
  extern __shared__ __align__(1024) uint8_t smem[];
  const uint32_t sb = smem_u32(smem);
  const int warp = __shfl_sync(0xffffffff, (int)(threadIdx.x >> 5), 0);
  const int wg = warp >> 2;
  const int rank = blockIdx.x & 1;
  const int g = blockIdx.x >> 3, pi = (blockIdx.x >> 1) & 3;
  const int br = g >> 3, b = g & 7;

  if (blockIdx.x >= 128) {
    if (warp < 4) {
      const int hg = (blockIdx.x - 128) * 4 + warp, hbr = hg >> 3, hb = hg & 7, lane = threadIdx.x & 31;
      const unsigned epoch = g_epoch[blockIdx.x];
      const uint64_t pol = policy_evict_first();
#pragma unroll 1
      for (int t = 0; t < 4; t++) {
        if (t > 0) flag_wait_soft(&g_cnt[(hg * 4 + t - 1) * 32 + 16], 8u * epoch + 4u);
#pragma unroll 1
        for (int q = 0; q < (t == 0 ? 3 : 4); q++) {
          const int i = 6 + 5 * q;
          if (lane < 8)
            bulk_prefetch((kv_is_k(i) ? p.k_ptr[hbr] : p.v_ptr[hbr]) + ((size_t)((hb * kH + 8 * t + lane) * kSk + kv_tile(i) * 64) << 8),
                          KV_BYTES, pol);
        }
      }
      __syncwarp();
    }
    __syncthreads();
    if (threadIdx.x == 0) g_epoch[blockIdx.x] = g_epoch[blockIdx.x] + 1u;
    return;
  }

  if (warp == 8) {
    if (elect_one()) {
      if (sb & 1023) asm volatile("trap;");
#pragma unroll
      for (int i = 0; i < NBAR; i++) {
        mbar_init(sb + BAR_FULL + i * 8, 1);
        mbar_init(sb + BAR_EMPTY + i * 8, 4);
      }
#pragma unroll
      for (int i = 0; i < 2; i++) {
        mbar_init(sb + BAR_ORDY + i * 8, 128);
        st_shared_u32(sb + OFF_FLAG + i * 4, 0);
      }
      mbar_init(sb + BAR_EXT, 6);
      asm volatile("fence.mbarrier_init.release.cluster;" ::: "memory");
      asm volatile("fence.acq_rel.cta;" ::: "memory");
    }
    __syncwarp();
  }
  asm volatile("barrier.cluster.arrive.relaxed.aligned;\nbarrier.cluster.wait.aligned;" ::: "memory");

  if (wg == 2) {
    asm volatile("setmaxnreg.dec.sync.aligned.u32 24;");
    if (warp == 8) {
      const unsigned epoch = g_epoch[blockIdx.x];
      const uint64_t pol = policy_evict_first();
      uint32_t n = 0, tail = 0;
      auto acquire = [&](uint32_t need) {
#pragma unroll 1
        for (; tail < need; tail++) mbar_wait(sb + BAR_EMPTY + (tail & (NBAR - 1)) * 8, stage_parity(tail));
      };
      const int jt = 2 * pi + rank;
#pragma unroll 1
      for (int t = 0; t < 4; t++) {
        const int h = 8 * t + jt;
        const int row0 = (b * kH + h) * kSk;
        uint32_t off = 0;
#pragma unroll 1
        for (int kc = 0; kc < 32; kc++, n++) {
          acquire(kc >= 20 ? n - 5 : (kc >= 7 ? n - 6 : (t == 0 ? 0u : n - kc - 7 + ((kDepProj >> (4 * kc)) & 15))));
          const uint32_t fb = sb + BAR_FULL + (n & (NBAR - 1)) * 8, sa = sb + OFF_RING + off * 16;
          off = proj_next16(off, kc + 1, false);
          if (elect_one()) {
            mbar_expect_tx(fb, PROJ_BYTES);
            tma_load_3d(sa, &p.wq[br], 0, kc * 32, 2 * h, fb);
            tma_load_2d_mc(sa + 8192 + rank * 7168, &p.x[br], kc * 32, b * kSq + rank * 112, fb, 3);
            if (t > 0 && (kc == 3 || kc == 4)) bulk_prefetch(p.k_ptr[br] + ((size_t)(row0 + (kc - 3) * 64) << 8), KV_BYTES, pol);
            if (kc >= 8 && kc < 24) bulk_prefetch(p.k_ptr[br] + ((size_t)(row0 + 128) << 8) + (kc - 8) * 1024, 1024, pol);
          }
        }
#pragma unroll 1
        for (int i = 0; i < 32; i++, n++) {
          acquire(i >= 8 ? n - 7 : n - i - 7 + ((kDepKV >> (4 * i)) & 15));
          const uint32_t fb = sb + BAR_FULL + (n & (NBAR - 1)) * 8, sa = sb + OFF_RING + kv_off16(i) * 16;
          if (i >= 3) mbar_wait(sb + BAR_FULL + ((n - 3) & (NBAR - 1)) * 8, stage_parity(n - 3));
          if (elect_one()) {
            mbar_expect_tx(fb, KV_BYTES);
            tma_load_3d_hint(sa, kv_is_k(i) ? &p.k[br] : &p.v[br], 0, row0 + kv_tile(i) * 64, 0, fb, pol);
            if (i == 31) asm volatile("red.relaxed.gpu.global.add.u32 [%0], 1;" ::"l"(&g_cnt[(g * 4 + t) * 32 + 16]) : "memory");
          }
        }
      }
      uint32_t off = 0;
#pragma unroll 1
      for (int kc = 0; kc < 128; kc++, n++) {
        const int round = (0x0132 >> (4 * (kc >> 5))) & 3, k0 = round * 1024 + (kc & 31) * 32;
        if ((kc & 31) == 0) {
          flag_wait(&g_cnt[(g * 4 + round) * 32], 24u * (epoch + 1u));
          asm volatile("fence.proxy.async;" ::: "memory");
        }
        if (kc == 7) mbar_wait(sb + BAR_EXT, 1);
        acquire(kc >= 10 ? n - 9 : (kc >= 7 ? 0u : n - kc - 7 + ((kDepProj >> (4 * kc)) & 15)));
        const uint32_t fb = sb + BAR_FULL + (n & (NBAR - 1)) * 8, sa = sb + OFF_RING + off * 16;
        off = proj_next16(off, kc + 1, true);
        if (elect_one()) {
          mbar_expect_tx(fb, PROJ_BYTES);
          tma_load_3d(sa, &p.wo[br], 0, k0, 2 * jt, fb);
          tma_load_2d_mc(sa + 8192 + rank * 7168, &p.o_ld, k0, g * kSq + rank * 112, fb, 3);
        }
      }
      if (threadIdx.x == 256) g_epoch[blockIdx.x] = epoch + 1u;
    } else {
      const int w = warp - 9, lane = threadIdx.x & 31;
#pragma unroll 1
      for (int u = 0; u < 4; u++) {
        const int h = 8 * u + 2 * pi + rank;
        if (u < 3) {
          const uint32_t d4 = 512 + ((((lane & 7) ^ ((lane >> 3) + 4)) - ((lane & 7) ^ (lane >> 3))) << 4);
#pragma unroll 1
          for (int cw = 0; cw < 2; cw++) {
            mbar_wait_sleep(sb + BAR_ORDY + cw * 8, u & 1);
            char* dst = p.o_ptr + (size_t)(g * kSq + cw * 112 + w * 40 + (lane >> 3)) * (kHD * 2) + h * 256 + (lane & 7) * 16;
            uint32_t a0 = sb + OFF_Q + cw * P_WG + (w * 40 + (lane >> 3)) * 128 + (((lane & 7) ^ (lane >> 3)) << 4);
#pragma unroll 1
            for (int i = w == 2 ? 1 : 0; i < 5; i++) {
              const uint4 v0 = ld_shared_u4(a0), v1 = ld_shared_u4(a0 + Q_HALF), v2 = ld_shared_u4(a0 + d4), v3 = ld_shared_u4(a0 + d4 + Q_HALF);
              st_global_u4(dst, v0);
              st_global_u4(dst + 128, v1);
              st_global_u4(dst + 4 * kHD * 2, v2);
              st_global_u4(dst + 4 * kHD * 2 + 128, v3);
              dst += 8 * kHD * 2;
              a0 += 1024;
            }
          }
          __syncwarp();
        } else {
          mbar_wait_sleep(sb + BAR_ORDY + (w ? 8 : 0), 1);
          if (lane == 0 && w < 2) {
            tma_store_2d(&p.o_st, sb + OFF_Q + w * P_WG, h * 128, g * kSq + w * 112);
            tma_store_2d(&p.o_st, sb + OFF_Q + w * P_WG + Q_HALF, h * 128 + 64, g * kSq + w * 112);
            asm volatile("cp.async.bulk.commit_group;" ::: "memory");
            asm volatile("cp.async.bulk.wait_group.read 0;" ::: "memory");
          }
        }
        if (lane == 0) {
          asm volatile("mbarrier.arrive.shared::cluster.b64 _, [%0];" ::"r"(map_to_cta(sb + BAR_EXT, 0)) : "memory");
          asm volatile("mbarrier.arrive.shared::cluster.b64 _, [%0];" ::"r"(map_to_cta(sb + BAR_EXT, 1)) : "memory");
          if (u == 3) {
            asm volatile("cp.async.bulk.wait_group 0;" ::: "memory");
            asm volatile("fence.proxy.async;" ::: "memory");
          }
        }
        asm volatile("fence.acq_rel.gpu;" ::: "memory");
        __syncwarp();
        if (lane == 0) asm volatile("red.relaxed.gpu.global.add.u32 [%0], 1;" ::"l"(&g_cnt[(g * 4 + u) * 32]) : "memory");
      }
    }
  } else {
    asm volatile("setmaxnreg.inc.sync.aligned.u32 240;");
    const int w = wg;
    const int lane = threadIdx.x & 31, wq4 = warp & 3;
    const uint32_t st_off = (uint32_t)((((lane >> 4) << 3) + (lane & 7)) * 128 + (((2 * wq4 + ((lane >> 3) & 1)) ^ (lane & 7)) << 4));
    const uint32_t q_addr = sb + OFF_Q + w * P_WG;
    const uint32_t p_addr = sb + OFF_P + w * P_WG;
    const uint32_t qbase16 = desc_lo(q_addr);
    const uint32_t red_addr = sb + OFF_RED + w * 1792;
    const uint32_t res_addr = sb + OFF_RES + w * 448;
    const uint32_t flag_addr = sb + OFF_FLAG + w * 4;
    const int bar_wg = 1 + w, bar_vote = 3 + w;
    const int my_turn = 5 + w, other_turn = 6 - w;
    Ctx cx;
    cx.sb = sb;
    cx.ring16 = desc_lo(sb + OFF_RING);
    cx.rel = map_to_cta(sb + BAR_EMPTY, warp & 1);
    cx.do_rel = (warp & 2) ^ 2;
    uint32_t n = 0;
    float o0[56], o1[56];
    if (w == 1) bar_arrive(other_turn, 256);

#pragma unroll 1
    for (int t = 0; t < 4; t++) {
      {
        uint32_t off = 0;
#pragma unroll 1
        for (int it = 0; it < 32; it++) {
          const uint32_t da = cx.ring16 + off;
          off = proj_next16(off, it + 1, false);
          const uint32_t db = da + 512 + w * 448;
          mbar_wait(full_bar(cx, n), stage_parity(n));
          wg_fence();
          wgmma_n112<1>(o0, desc(da, DESC_SW128), desc(db, DESC_SW64), it);
          wgmma_n112<1>(o1, desc(da + 256, DESC_SW128), desc(db, DESC_SW64), it);
          wgmma_n112<1>(o0, desc(da + 128, DESC_SW128), desc(db + 2, DESC_SW64), 1);
          wgmma_n112<1>(o1, desc(da + 256 + 128, DESC_SW128), desc(db + 2, DESC_SW64), 1);
          wg_commit();
          if (it == 0 && t > 0) mbar_arrive(sb + BAR_ORDY + w * 8);
          wg_wait<1>();
          if (it > 0) release_stage(cx, n - 1);
          n++;
        }
        mbar_wait(sb + BAR_EXT, (t & 1) ^ 1);
        wg_wait<0>();
        pin(o0);
        pin(o1);
        release_stage(cx, n - 1);
        store_tile_t(q_addr + st_off, o0);
        store_tile_t(q_addr + Q_HALF + st_off, o1);
        mbar_wait(full_bar(cx, n), stage_parity(n));
        fence_async_smem();
      }
      float s[56], l[28], nm[14];
      bool exact_mode = false;
      uint32_t nk = n, kprev16 = cx.ring16 + kv_off16(0);
      uint32_t k16 = cx.ring16 + kv_off16(1), v16 = cx.ring16 + kv_off16(2);
      uint32_t q16 = qbase16 + p.zero * t;
      {
        uint32_t pk[28];
        float t0, t1;
        bar_sync(my_turn, 256);
        wg_fence();
        issue_s(kprev16, q16, s);
        wg_commit();
        bar_arrive(other_turn, 256);
        if ((threadIdx.x & 127) < 28) st_shared_u4(res_addr + (threadIdx.x & 127) * 16, 0xc2240000u, 0xc2240000u, 0xc2240000u, 0xc2240000u);
#pragma unroll
        for (int i = 0; i < 28; i++) l[i] = 0.f;
        wg_wait<0>();
        pin(s);
        const float ref = first_reference(red_addr, bar_wg, wq4, s);
#pragma unroll
        for (int i = 0; i < 14; i++) nm[i] = ref;
        exp_cols<0, 12>(s, nm);
        sum_pack_cols<0, 10>(s, pk, l, t0, t1);
        store_p<0, 10>(p_addr + st_off, pk);
        pin_range<40, 48>(s);
        mbar_wait(full_bar(cx, n + 1), stage_parity(n + 1));
        exp_cols<12, 14>(s, nm);
        sum_pack_cols<10, 14>(s, pk, l, t0, t1);
        store_p<10, 14>(p_addr + st_off, pk);
        int lo = __vimin3_s32(__float_as_int(l[0]), __float_as_int(l[1]), __float_as_int(l[2]));
        int lo2 = __float_as_int(l[3]);
#pragma unroll
        for (int i = 4; i < 28; i += 4) {
          lo = __vimin3_s32(lo, __float_as_int(l[i]), __float_as_int(l[i + 1]));
          lo2 = __vimin3_s32(lo2, __float_as_int(l[i + 2]), __float_as_int(l[i + 3]));
        }
        if (!(t0 + t1 < kSumLimit) || min(lo, lo2) < 0x2b800000) st_shared_u32(flag_addr, 1);
        fence_async_smem();
      }
      auto redo_tile = [&](bool fresh) {
        uint32_t pk[28];
        wg_wait<0>();
        wg_fence();
        issue_s(kprev16, q16, s);
        wg_commit();
        wg_wait<0>();
        pin(s);
#pragma unroll
        for (int i = 0; i < 56; i++) s[i] = fmaf(s[i], kScale, nm[i >> 2]);
        exact_mode = exact_tile(red_addr, res_addr, bar_wg, bar_vote, lane, wq4, fresh, !exact_mode, s, pk, nm, l, o0, o1);
        store_p<0, 14>(p_addr + st_off, pk);
        st_shared_u32(flag_addr, 0);
        fence_async_smem();
        bar_sync(bar_wg, 128);
      };
#pragma unroll 1
      for (int j = 0; j < 15; j++) {
        bar_sync(my_turn, 256);
        wg_fence();
        issue_s(k16, q16, s);
        wg_commit();
        const uint32_t flag = ld_shared_u32(flag_addr);
        mbar_wait(full_bar(cx, n + 2), stage_parity(n + 2));
        if (__builtin_expect(__any_sync(0xffffffff, flag != 0), 0)) {
          redo_tile(j == 0);
          wg_fence();
          issue_s(k16, q16, s);
          wg_commit();
        }
        release_stage(cx, nk);
        wg_fence();
        issue_pv(v16, q16 - ((OFF_Q - OFF_P) >> 4), o0, o1, j);
        wg_commit();
        bar_arrive(other_turn, 256);
        nk = n + 1;
        n += 2;
        kprev16 = k16;
        k16 = cx.ring16 + kv_off16(n + 1);
        v16 = cx.ring16 + kv_off16(n + 2);
        q16 = qbase16 + p.zero * j;
        if (__builtin_expect(exact_mode, 0)) {
          wg_wait<0>();
          pin(s);
          pin(o0);
          pin(o1);
          release_stage(cx, n);
          mbar_wait(full_bar(cx, n + 1), stage_parity(n + 1));
          st_shared_u32(flag_addr, 1);
          continue;
        }
        float t0, t1;
        uint32_t pk[28];
        wg_wait<1>();
        pin(s);
        exp_cols<0, 6>(s, nm);
        sum_pack_cols<0, 4>(s, pk, l, t0, t1);
        pin_p<0, 4>(pk, l);
        pin_range<16, 24>(s);
        mbar_wait(full_bar(cx, n), stage_parity(n));
        wg_wait<0>();
        pin(o0);
        pin(o1);
        release_stage(cx, n);
        store_p<0, 4>(p_addr + st_off, pk);
        exp_cols<6, 12>(s, nm);
        sum_pack_cols<4, 10>(s, pk, l, t0, t1);
        store_p<4, 10>(p_addr + st_off, pk);
        pin_range<40, 48>(s);
        mbar_wait(full_bar(cx, n + 1), stage_parity(n + 1));
        exp_cols<12, 14>(s, nm);
        sum_pack_cols<10, 14>(s, pk, l, t0, t1);
        store_p<10, 14>(p_addr + st_off, pk);
        if (!(t0 + t1 < kSumLimit)) st_shared_u32(flag_addr, 1);
        fence_async_smem();
      }
      float lc[4];
      reduce_l_lanes(lane, l, lc);
      bar_sync(my_turn, 256);
      if (__builtin_expect(__any_sync(0xffffffff, ld_shared_u32(flag_addr) != 0), 0)) {
        redo_tile(false);
        reduce_l_lanes(lane, l, lc);
      }
      wg_fence();
      issue_pv(k16, q16 - ((OFF_Q - OFF_P) >> 4), o0, o1, 1);
      wg_commit();
      if (!(t == 3 && w == 1)) bar_arrive(other_turn, 256);
      release_stage(cx, nk);
      n += 2;
      SCHED_FENCE();
      reduce_l_warps(red_addr, bar_wg, lane, wq4, lc, l);
      wg_wait<0>();
      pin(o0);
      pin(o1);
      release_stage(cx, n - 1);
#pragma unroll
      for (int c = 0; c < 14; c++) {
        o0[4 * c] *= l[2 * c]; o0[4 * c + 2] *= l[2 * c]; o0[4 * c + 1] *= l[2 * c + 1]; o0[4 * c + 3] *= l[2 * c + 1];
        o1[4 * c] *= l[2 * c]; o1[4 * c + 2] *= l[2 * c]; o1[4 * c + 1] *= l[2 * c + 1]; o1[4 * c + 3] *= l[2 * c + 1];
      }
      store_tile_t(q_addr + st_off, o0);
      store_tile_t(q_addr + Q_HALF + st_off, o1);
      if (t == 3) {
        fence_async_smem();
        mbar_arrive(sb + BAR_ORDY + w * 8);
      }
    }
    float acc[112];
    uint32_t off = 0;
#pragma unroll 1
    for (int it = 0; it < 128; it++) {
      const uint32_t da = cx.ring16 + off + w * 256, db = cx.ring16 + off + 512;
      off = proj_next16(off, it + 1, true);
      mbar_wait(full_bar(cx, n), stage_parity(n));
      wg_fence();
      wgmma_n224<1>(acc, desc(da, DESC_SW128), desc(db, DESC_SW64), it);
      wgmma_n224<1>(acc, desc(da + 128, DESC_SW128), desc(db + 2, DESC_SW64), 1);
      wg_commit();
      wg_wait<1>();
      if (it > 0 && it <= 118) release_stage(cx, n - 1);
      n++;
    }
    wg_wait<0>();
    pin(acc);
    bar_sync(7, 256);
    const int c0 = br * kD + (2 * pi + rank) * 128 + w * 64;
    const uint32_t stg = sb + OFF_Q + w * Q_HALF;
#pragma unroll
    for (int hf = 0; hf < 2; hf++) {
#pragma unroll
      for (int c = 14 * hf; c < 14 * hf + 14; c += 2)
        stsm_x4_t(stg + st_off + c * 1024, pack_bf16(acc[4 * c + 0], acc[4 * c + 1]), pack_bf16(acc[4 * c + 2], acc[4 * c + 3]),
                  pack_bf16(acc[4 * c + 4], acc[4 * c + 5]), pack_bf16(acc[4 * c + 6], acc[4 * c + 7]));
      fence_async_smem();
      bar_sync(bar_wg, 128);
      if ((threadIdx.x & 127) == 0) tma_store_2d(&p.out_st, stg + hf * P_WG, c0, b * kSq + hf * 112);
    }
    if ((threadIdx.x & 127) == 0) {
      asm volatile("cp.async.bulk.commit_group;" ::: "memory");
      asm volatile("cp.async.bulk.wait_group.read 0;" ::: "memory");
    }
  }
}

typedef CUresult (*EncodeFn)(CUtensorMap*, CUtensorMapDataType, cuuint32_t, void*, const cuuint64_t*, const cuuint64_t*,
                             const cuuint32_t*, const cuuint32_t*, CUtensorMapInterleave, CUtensorMapSwizzle,
                             CUtensorMapL2promotion, CUtensorMapFloatOOBfill);

bool make_map(EncodeFn enc, CUtensorMap* m, const void* ptr, int rank, const cuuint64_t* gd, const cuuint64_t* gs, const cuuint32_t* bd,
              CUtensorMapSwizzle swz) {
  cuuint32_t es[3] = {1, 1, 1};
  return enc(m, CU_TENSOR_MAP_DATA_TYPE_BFLOAT16, rank, const_cast<void*>(ptr), gd, gs, bd, es, CU_TENSOR_MAP_INTERLEAVE_NONE, swz,
             CU_TENSOR_MAP_L2_PROMOTION_L2_128B, CU_TENSOR_MAP_FLOAT_OOB_FILL_NONE) == CUDA_SUCCESS;
}
bool map_2d(EncodeFn enc, CUtensorMap* m, const void* ptr, uint64_t rows, uint64_t cols, uint32_t box_rows, uint32_t box_cols,
            CUtensorMapSwizzle swz) {
  cuuint64_t gd[2] = {cols, rows}, gs[1] = {cols * 2};
  cuuint32_t bd[2] = {box_cols, box_rows};
  return make_map(enc, m, ptr, 2, gd, gs, bd, swz);
}
bool map_panels(EncodeFn enc, CUtensorMap* m, const void* ptr, uint64_t rows, uint64_t cols, uint32_t box_rows) {
  cuuint64_t gd[3] = {64, rows, cols / 64}, gs[2] = {cols * 2, 128};
  cuuint32_t bd[3] = {64, box_rows, 2};
  return make_map(enc, m, ptr, 3, gd, gs, bd, CU_TENSOR_MAP_SWIZZLE_128B);
}

}

extern "C" void kernel_launch(void* const* d_in, const int* in_sizes, int n_in, void* d_out, int out_size) {
  (void)in_sizes; (void)n_in; (void)out_size;
  static EncodeFn enc = nullptr;
  static void* o_ptr = nullptr;
  static int grid = 128;
  if (!enc) {
    void* fn = nullptr;
    cudaDriverEntryPointQueryResult q;
    cudaGetDriverEntryPoint("cuTensorMapEncodeTiled", &fn, cudaEnableDefault, &q);
    enc = (EncodeFn)fn;
    cudaGetSymbolAddress(&o_ptr, g_o);
    cudaFuncSetAttribute(fused_kernel, cudaFuncAttributeMaxDynamicSharedMemorySize, SMEM_BYTES);
    cudaLaunchConfig_t cfg = {};
    cfg.gridDim = dim3(132);
    cfg.blockDim = dim3(384);
    cfg.dynamicSmemBytes = SMEM_BYTES;
    cudaLaunchAttribute at[1];
    at[0].id = cudaLaunchAttributeClusterDimension;
    at[0].val.clusterDim.x = 2;
    at[0].val.clusterDim.y = 1;
    at[0].val.clusterDim.z = 1;
    cfg.attrs = at;
    cfg.numAttrs = 1;
    int clusters = 0;
    if (cudaOccupancyMaxActiveClusters(&clusters, fused_kernel, &cfg) == cudaSuccess && clusters >= 66) grid = 132;
    (void)cudaGetLastError();
  }
  Params p;
  p.zero = 0;
  p.o_ptr = (char*)o_ptr;
  bool ok = true;
  for (int br = 0; br < 2; br++) {
    const void* x = d_in[5 * br + 0];
    const void* k = d_in[5 * br + 1];
    const void* v = d_in[5 * br + 2];
    const void* wq = d_in[5 * br + 3];
    const void* wo = d_in[5 * br + 4];
    p.k_ptr[br] = (const char*)k;
    p.v_ptr[br] = (const char*)v;
    ok &= map_2d(enc, &p.x[br], x, kRows, kD, 112, 32, CU_TENSOR_MAP_SWIZZLE_64B);
    ok &= map_panels(enc, &p.wq[br], wq, kD, kHD, 32);
    ok &= map_panels(enc, &p.k[br], k, (uint64_t)kB * kH * kSk, kDh, 64);
    ok &= map_panels(enc, &p.v[br], v, (uint64_t)kB * kH * kSk, kDh, 64);
    ok &= map_panels(enc, &p.wo[br], wo, kHD, kD, 32);
  }
  ok &= map_2d(enc, &p.o_st, o_ptr, 2 * kRows, kHD, 112, 64, CU_TENSOR_MAP_SWIZZLE_128B);
  ok &= map_2d(enc, &p.o_ld, o_ptr, 2 * kRows, kHD, 112, 32, CU_TENSOR_MAP_SWIZZLE_64B);
  ok &= map_2d(enc, &p.out_st, d_out, kRows, 2 * kD, 112, 64, CU_TENSOR_MAP_SWIZZLE_128B);
  if (!ok) return;
  fused_kernel<<<grid, 384, SMEM_BYTES>>>(p);
}
```
